```python
import torch

def _softmax(x, axis=-1):
    return torch.softmax(x, dim=axis)
def _gelu(x):
    return torch.nn.functional.gelu(x, approximate="tanh")
def _silu(x):
    return torch.nn.functional.silu(x)
def _sigmoid(x):
    return torch.sigmoid(x)
def _layernorm(x, axis=-1, eps=1e-5):
    m = x.mean(dim=axis, keepdim=True)
    v = x.var(dim=axis, keepdim=True, unbiased=False)
    return (x - m) / torch.sqrt(v + eps)
def _scatter_add(tgt, idx, src, axis=0):
    return tgt.clone().index_add_(axis, idx, src)
def _segment_sum(src, seg, n):
    out = torch.zeros((n,) + src.shape[1:], dtype=src.dtype)
    return out.index_add_(0, seg, src)
def _pad(x, pw):
    flat = tuple(v for pair in reversed(pw) for v in pair)
    return torch.nn.functional.pad(x, flat)

kernel_name = 'recurrent_scan__sliding_block_cached__dense_activation_silu__decode'

def setup_inputs():

    _w = (lambda a: (lambda t: t.to(torch.bfloat16) if t.is_floating_point() else t)(torch.as_tensor(a)))
    def _A_setup():
        B, Sq, D = 4, 1, 576
        Hq, Hkv, Sk, Dh = 32, 16, 4096, 128
        assert Hq % Hkv == 0, (Hq, Hkv)
        return {
            "x": _w((lambda *s: torch.randn(*s, dtype=torch.bfloat16) * 0.1)(B, Sq, D)),
            "k_cache": _w((lambda *s: torch.randn(*s, dtype=torch.bfloat16) * 0.8)(B, Hkv, Sk, Dh)),
            "v_cache": _w((lambda *s: torch.randn(*s, dtype=torch.bfloat16) * 3.2)(B, Hkv, Sk, Dh)),
            "wq": _w((lambda *s: torch.randn(*s, dtype=torch.bfloat16) * 0.8)(D, Hq * Dh) * (D ** -0.5)),
            "wo": _w((lambda *s: torch.randn(*s, dtype=torch.bfloat16) * 3.2)(Hq * Dh, D) * ((Hq * Dh) ** -0.5)),
        }
    _A_in = _A_setup()

    def _B_setup():
        B, S, D, F = 4, 1, 576, 4608
        return {
            "x": _w((lambda *s: torch.randn(*s, dtype=torch.bfloat16) * 0.1)(B, S, D)),
            "w1": _w((lambda *s: torch.randn(*s, dtype=torch.bfloat16) * 3.2)(D, F) * (D ** -0.5)),
            "w2": _w((lambda *s: torch.randn(*s, dtype=torch.bfloat16) * 3.2)(F, D) * (F ** -0.5)),
        }
    _B_in = _B_setup()

    return {
        "A_x": _A_in["x"],
        "A_k_cache": _A_in["k_cache"],
        "A_v_cache": _A_in["v_cache"],
        "A_wq": _A_in["wq"],
        "A_wo": _A_in["wo"],
        "B_x": _B_in["x"],
        "B_w1": _B_in["w1"],
        "B_w2": _B_in["w2"],
    }

def reference(A_x, A_k_cache, A_v_cache, A_wq, A_wo, B_x, B_w1, B_w2):
    def _A_ref(x, k_cache, v_cache, wq, wo):
        B, Sq, D = x.shape
        Hq, Dh = 32, 128
        Hkv, Sk = k_cache.shape[1], k_cache.shape[2]
        W = min(4096, max(256, Sk // 4))
        rep = Hq // Hkv
        q = (lambda x, *d: x.permute(*d))((x @ wq).reshape(B, Sq, Hq, Dh), 0, 2, 1, 3)
        k = (lambda x, n, axis: torch.repeat_interleave(x, n, dim=axis))(k_cache[:, :, Sk - W:, :], rep, axis=1)
        v = (lambda x, n, axis: torch.repeat_interleave(x, n, dim=axis))(v_cache[:, :, Sk - W:, :], rep, axis=1)
        scores = torch.einsum("bhqd,bhkd->bhqk", q, k) * (Dh ** -0.5)
        p = _softmax(scores, axis=-1)
        o = torch.einsum("bhqk,bhkd->bhqd", p, v)
        return (lambda x, *d: x.permute(*d))(o, 0, 2, 1, 3).reshape(B, Sq, Hq * Dh) @ wo

    def _B_ref(x, w1, w2):
        h = torch.einsum("bsd,df->bsf", x, w1)
        h = _silu(h)
        out = torch.einsum("bsf,fd->bsd", h, w2)
        return out

    x = A_x
    xn = _layernorm(x, axis=-1)
    s = _A_ref(xn, A_k_cache, A_v_cache, A_wq, A_wo)
    g = _silu(_B_ref(xn, B_w1, B_w2))
    return x + s * g
```

```cpp
#include <cuda_runtime.h>
#include <cuda_bf16.h>
#include <cuda.h>
#include <stdint.h>

typedef __nv_bfloat16 bf16;

namespace {

constexpr int DM = 576;
constexpr int HKV = 16;
constexpr int SK = 4096;
constexpr int DH = 128;
constexpr int WIN = 1024;
constexpr int FF = 4608;
constexpr int NCTA = 128;
constexpr int NTHREADS = 288;

constexpr int KROWS = 72;
constexpr int WQ_PITCH = 528;
constexpr int W1_PITCH = 592;
constexpr int WO_PITCH = 144;
constexpr int STAGE_BYTES = 16384;
constexpr int NSTAGE = 8;

constexpr int OFF_KV = 0;
constexpr int OFF_A = NSTAGE * STAGE_BYTES;
constexpr int OFF_WQ = OFF_A;
constexpr int OFF_W1 = OFF_WQ + KROWS * WQ_PITCH;
constexpr int OFF_WO = OFF_A;
constexpr int OFF_W2 = OFF_WO + 256 * WO_PITCH;
constexpr int OFF_MISC = OFF_W1 + KROWS * W1_PITCH;
constexpr int OFF_XN = OFF_MISC;
constexpr int OFF_Q = OFF_XN + 4 * 80 * 2;
constexpr int OFF_P = OFF_Q + 2 * 136 * 2;
constexpr int OFF_HS = OFF_P + 2 * 520 * 2;
constexpr int OFF_OS = OFF_HS + 4 * 296 * 2;
constexpr int OFF_WMAX = OFF_OS + 4 * 264 * 2;
constexpr int OFF_WSUM = OFF_WMAX + 64;
constexpr int OFF_CW = OFF_WSUM + 64;
constexpr int OFF_BAR = OFF_CW + 64;
constexpr int OFF_END = OFF_BAR + 32 * 8;
constexpr int OFF_RED = OFF_KV;
constexpr int SMEM_BYTES = OFF_END + 1024;
static_assert(OFF_BAR % 8 == 0, "bar align");
static_assert(OFF_W2 % 128 == 0, "w2 align");
static_assert(SMEM_BYTES <= 232448, "smem");

constexpr int BAR_FULL = 0;
constexpr int BAR_EMPTY = 8;
constexpr int BAR_W = 16;
constexpr int BAR_P1 = 17;
constexpr int BAR_WO = 18;
constexpr int BAR_W2 = 19;

constexpr unsigned SPIN_MAX = 1u << 22;

__device__ float g_qh[16 * 8 * 4 * 544];
__device__ unsigned g_flag1[NCTA];
__device__ uint2 g_o[NCTA * 264];
__device__ uint2 g_fin[8 * 16 * 576];
__device__ unsigned g_epoch[NCTA];

__device__ __forceinline__ void mbar_init(uint32_t bar, uint32_t cnt) {
    asm volatile("mbarrier.init.shared::cta.b64 [%0], %1;" ::"r"(bar), "r"(cnt) : "memory");
}
__device__ __forceinline__ void mbar_expect_tx(uint32_t bar, uint32_t bytes) {
    asm volatile("mbarrier.arrive.expect_tx.shared::cta.b64 _, [%0], %1;" ::"r"(bar), "r"(bytes) : "memory");
}
__device__ __forceinline__ void mbar_arrive(uint32_t bar) {
    asm volatile("mbarrier.arrive.shared::cta.b64 _, [%0];" ::"r"(bar) : "memory");
}
__device__ __forceinline__ void mbar_wait(uint32_t bar, uint32_t parity) {
    unsigned it = 0;
    uint32_t ok;
    do {
        asm volatile(
            "{\n.reg .pred p;\n"
            "mbarrier.try_wait.parity.shared::cta.b64 p, [%1], %2;\n"
            "selp.u32 %0, 1, 0, p;\n}\n"
            : "=r"(ok)
            : "r"(bar), "r"(parity)
            : "memory");
    } while (!ok && ++it < SPIN_MAX);
}
__device__ __forceinline__ void bulk_g2s(uint32_t dst, const void* src, uint32_t bytes, uint32_t bar) {
    asm volatile("cp.async.bulk.shared::cluster.global.mbarrier::complete_tx::bytes [%0], [%1], %2, [%3];" ::"r"(dst),
                 "l"(src), "r"(bytes), "r"(bar)
                 : "memory");
}
__device__ __forceinline__ void tma_2d(uint32_t dst, const CUtensorMap* tm, int c0, int c1, uint32_t bar) {
    asm volatile(
        "cp.async.bulk.tensor.2d.shared::cluster.global.mbarrier::complete_tx::bytes [%0], [%1, {%3, %4}], [%2];" ::"r"(dst),
        "l"(tm), "r"(bar), "r"(c0), "r"(c1)
        : "memory");
}
__device__ __forceinline__ void ldsm_x4(uint32_t addr, uint32_t& r0, uint32_t& r1, uint32_t& r2, uint32_t& r3) {
    asm volatile("ldmatrix.sync.aligned.m8n8.x4.shared.b16 {%0,%1,%2,%3}, [%4];"
                 : "=r"(r0), "=r"(r1), "=r"(r2), "=r"(r3)
                 : "r"(addr)
                 : "memory");
}
__device__ __forceinline__ void ldsm_x4_t(uint32_t addr, uint32_t& r0, uint32_t& r1, uint32_t& r2, uint32_t& r3) {
    asm volatile("ldmatrix.sync.aligned.m8n8.x4.trans.shared.b16 {%0,%1,%2,%3}, [%4];"
                 : "=r"(r0), "=r"(r1), "=r"(r2), "=r"(r3)
                 : "r"(addr)
                 : "memory");
}
__device__ __forceinline__ void ldsm_x2_t(uint32_t addr, uint32_t& r0, uint32_t& r1) {
    asm volatile("ldmatrix.sync.aligned.m8n8.x2.trans.shared.b16 {%0,%1}, [%2];"
                 : "=r"(r0), "=r"(r1)
                 : "r"(addr)
                 : "memory");
}
__device__ __forceinline__ void ldsm_x1_t(uint32_t addr, uint32_t& r0) {
    asm volatile("ldmatrix.sync.aligned.m8n8.x1.trans.shared.b16 {%0}, [%1];" : "=r"(r0) : "r"(addr) : "memory");
}
__device__ __forceinline__ void mma16816(float (&c)[4], uint32_t a0, uint32_t a1, uint32_t a2, uint32_t a3, uint32_t b0,
                                         uint32_t b1) {
    asm volatile(
        "mma.sync.aligned.m16n8k16.row.col.f32.bf16.bf16.f32 {%0,%1,%2,%3}, {%4,%5,%6,%7}, {%8,%9}, {%0,%1,%2,%3};"
        : "+f"(c[0]), "+f"(c[1]), "+f"(c[2]), "+f"(c[3])
        : "r"(a0), "r"(a1), "r"(a2), "r"(a3), "r"(b0), "r"(b1));
}
__device__ __forceinline__ void mma1688(float (&c)[4], uint32_t a0, uint32_t a1, uint32_t b0) {
    asm volatile("mma.sync.aligned.m16n8k8.row.col.f32.bf16.bf16.f32 {%0,%1,%2,%3}, {%4,%5}, {%6}, {%0,%1,%2,%3};"
                 : "+f"(c[0]), "+f"(c[1]), "+f"(c[2]), "+f"(c[3])
                 : "r"(a0), "r"(a1), "r"(b0));
}
__device__ __forceinline__ void cbar() { asm volatile("bar.sync 1, 256;" ::: "memory"); }
__device__ __forceinline__ float bfr(float v) { return __bfloat162float(__float2bfloat16_rn(v)); }
__device__ __forceinline__ uint32_t lds32(uint32_t addr) {
    uint32_t v;
    asm volatile("ld.shared.b32 %0, [%1];" : "=r"(v) : "r"(addr) : "memory");
    return v;
}
__device__ __forceinline__ uint2 ld_ll(const uint2* p) {
    uint2 v;
    asm volatile("ld.relaxed.gpu.global.v2.u32 {%0,%1}, [%2];" : "=r"(v.x), "=r"(v.y) : "l"(p) : "memory");
    return v;
}
__device__ __forceinline__ void st_ll(uint2* p, float val, unsigned tag) {
    asm volatile("st.relaxed.gpu.global.v2.u32 [%0], {%1,%2};" ::"l"(p), "r"(__float_as_uint(val)), "r"(tag) : "memory");
}
__device__ __forceinline__ float silu_f(float v) { return v / (1.0f + __expf(-v)); }

__global__ void __launch_bounds__(NTHREADS, 1)
fused_decode_kernel(const __grid_constant__ CUtensorMap tmK, const __grid_constant__ CUtensorMap tmV,
                    const __grid_constant__ CUtensorMap tmWo, const __grid_constant__ CUtensorMap tmW2,
                    const bf16* __restrict__ x, const bf16* __restrict__ wq, const bf16* __restrict__ w1,
                    bf16* __restrict__ out) {
    extern __shared__ uint8_t smem_raw[];
    const uint32_t sb = (((uint32_t)__cvta_generic_to_shared(smem_raw)) + 1023u) & ~1023u;
    uint8_t* sp = smem_raw + (sb - (uint32_t)__cvta_generic_to_shared(smem_raw));

    const int tid = threadIdx.x;
    const int warp = tid >> 5;
    const int lane = tid & 31;
    const int cta = blockIdx.x;
    const int grp = cta >> 3;
    const int r = cta & 7;
    const int bb = r >> 1;
    const int split = r & 1;
    const uint32_t bar0 = sb + OFF_BAR;

    if (tid == 256) {
        for (int i = 0; i < NSTAGE; i++) {
            mbar_init(bar0 + (BAR_FULL + i) * 8, 1);
            mbar_init(bar0 + (BAR_EMPTY + i) * 8, 4);
        }
        mbar_init(bar0 + BAR_W * 8, 1);
        mbar_init(bar0 + BAR_P1 * 8, 8);
        mbar_init(bar0 + BAR_WO * 8, 1);
        for (int i = 0; i < 3; i++) mbar_init(bar0 + (BAR_W2 + i) * 8, 1);
        asm volatile("fence.mbarrier_init.release.cluster;" ::: "memory");
        asm volatile("fence.proxy.async.shared::cta;" ::: "memory");
    }
    __syncthreads();

    if (warp == 8) {
        if (lane == 0) {
            asm volatile("prefetch.tensormap [%0];" ::"l"(&tmK) : "memory");
            mbar_expect_tx(bar0 + BAR_W * 8, KROWS * (512 + 576));
        }
        __syncwarp();
        for (int i = lane; i < KROWS; i += 32) {
            bulk_g2s(sb + OFF_WQ + i * WQ_PITCH, wq + (size_t)(r * KROWS + i) * 4096 + grp * 256, 512, bar0 + BAR_W * 8);
            bulk_g2s(sb + OFF_W1 + i * W1_PITCH, w1 + (size_t)(r * KROWS + i) * FF + grp * 288, 576, bar0 + BAR_W * 8);
        }
        if (lane == 0) {
            const int row0 = (bb * HKV + grp) * SK + (SK - WIN) + split * 512;
            for (int s = 0; s < NSTAGE; s++) {
                mbar_expect_tx(bar0 + (BAR_FULL + s) * 8, STAGE_BYTES);
                tma_2d(sb + OFF_KV + s * STAGE_BYTES, &tmK, 0, row0 + s * 64, bar0 + (BAR_FULL + s) * 8);
                tma_2d(sb + OFF_KV + s * STAGE_BYTES + 8192, &tmK, 64, row0 + s * 64, bar0 + (BAR_FULL + s) * 8);
            }
            asm volatile("prefetch.tensormap [%0];" ::"l"(&tmV) : "memory");
            asm volatile("prefetch.tensormap [%0];" ::"l"(&tmWo) : "memory");
            asm volatile("prefetch.tensormap [%0];" ::"l"(&tmW2) : "memory");
            mbar_wait(bar0 + BAR_P1 * 8, 0);
            mbar_expect_tx(bar0 + BAR_WO * 8, 256 * WO_PITCH);
            tma_2d(sb + OFF_WO, &tmWo, r * 72, grp * 256, bar0 + BAR_WO * 8);
            for (int s = 0; s < NSTAGE; s++) {
                mbar_wait(bar0 + (BAR_EMPTY + s) * 8, 0);
                mbar_expect_tx(bar0 + (BAR_FULL + s) * 8, STAGE_BYTES);
                tma_2d(sb + OFF_KV + s * STAGE_BYTES, &tmV, 0, row0 + s * 64, bar0 + (BAR_FULL + s) * 8);
                tma_2d(sb + OFF_KV + s * STAGE_BYTES + 8192, &tmV, 64, row0 + s * 64, bar0 + (BAR_FULL + s) * 8);
            }
            for (int i = 0; i < 3; i++) {
                mbar_expect_tx(bar0 + (BAR_W2 + i) * 8, 96 * WO_PITCH);
                tma_2d(sb + OFF_W2 + i * 96 * WO_PITCH, &tmW2, r * 72, grp * 288 + i * 96, bar0 + (BAR_W2 + i) * 8);
            }
        }
        return;
    }

    const int g = lane >> 2;
    const int t = lane & 3;
    const unsigned tag = g_epoch[cta] + 1u;

    if (warp < 4) {
        const uint32_t* xr = reinterpret_cast<const uint32_t*>(x + warp * DM);
        float v0[9], v1[9];
        float sum = 0.f;
#pragma unroll
        for (int i = 0; i < 9; i++) {
            uint32_t u = xr[lane + 32 * i];
            v0[i] = __uint_as_float(u << 16);
            v1[i] = __uint_as_float(u & 0xffff0000u);
            sum += v0[i] + v1[i];
        }
#pragma unroll
        for (int o = 16; o > 0; o >>= 1) sum += __shfl_xor_sync(0xffffffffu, sum, o);
        const float mean = sum * (1.0f / DM);
        float sq = 0.f;
#pragma unroll
        for (int i = 0; i < 9; i++) {
            float a = v0[i] - mean, c = v1[i] - mean;
            sq += a * a + c * c;
        }
#pragma unroll
        for (int o = 16; o > 0; o >>= 1) sq += __shfl_xor_sync(0xffffffffu, sq, o);
        const float mb = bfr(mean);
        const float vb = bfr(sq * (1.0f / DM));
        const float den = bfr(sqrtf(bfr(vb + 1e-5f)));
#pragma unroll
        for (int i = 0; i < 9; i++) {
            int pi = lane + 32 * i - r * 36;
            if (pi >= 0 && pi < 36) {
                __nv_bfloat162 o2;
                o2.x = __float2bfloat16_rn(bfr(v0[i] - mb) / den);
                o2.y = __float2bfloat16_rn(bfr(v1[i] - mb) / den);
                *reinterpret_cast<__nv_bfloat162*>(sp + OFF_XN + warp * 160 + pi * 4) = o2;
            }
        }
    }
    cbar();

    {
        uint32_t xa0[5], xa2[4];
#pragma unroll
        for (int ks = 0; ks < 5; ks++) {
            xa0[ks] = (g < 4) ? lds32(sb + OFF_XN + g * 160 + (ks * 16 + 2 * t) * 2) : 0u;
            if (ks < 4) xa2[ks] = (g < 4) ? lds32(sb + OFF_XN + g * 160 + (ks * 16 + 8 + 2 * t) * 2) : 0u;
        }
        float cq[4][4], ch[5][4];
#pragma unroll
        for (int j = 0; j < 4; j++)
#pragma unroll
            for (int i = 0; i < 4; i++) cq[j][i] = 0.f;
#pragma unroll
        for (int j = 0; j < 5; j++)
#pragma unroll
            for (int i = 0; i < 4; i++) ch[j][i] = 0.f;
        const int ht0 = (warp < 4) ? warp * 5 : 20 + (warp - 4) * 4;
        const bool has5 = warp < 4;
        mbar_wait(bar0 + BAR_W * 8, 0);
        const int lrow = (lane & 7) + ((lane >> 3) & 1) * 8;
        const int ltile = lane >> 4;
#pragma unroll
        for (int ks = 0; ks < 4; ks++) {
#pragma unroll
            for (int jp = 0; jp < 2; jp++) {
                uint32_t b0, b1, b2, b3;
                ldsm_x4_t(sb + OFF_WQ + (ks * 16 + lrow) * WQ_PITCH + (warp * 4 + jp * 2 + ltile) * 16, b0, b1, b2, b3);
                mma16816(cq[jp * 2], xa0[ks], 0u, xa2[ks], 0u, b0, b1);
                mma16816(cq[jp * 2 + 1], xa0[ks], 0u, xa2[ks], 0u, b2, b3);
                ldsm_x4_t(sb + OFF_W1 + (ks * 16 + lrow) * W1_PITCH + (ht0 + jp * 2 + ltile) * 16, b0, b1, b2, b3);
                mma16816(ch[jp * 2], xa0[ks], 0u, xa2[ks], 0u, b0, b1);
                mma16816(ch[jp * 2 + 1], xa0[ks], 0u, xa2[ks], 0u, b2, b3);
            }
            if (has5) {
                uint32_t b0, b1;
                ldsm_x2_t(sb + OFF_W1 + (ks * 16 + lrow) * W1_PITCH + (ht0 + 4) * 16, b0, b1);
                mma16816(ch[4], xa0[ks], 0u, xa2[ks], 0u, b0, b1);
            }
        }
        {
            uint32_t b0, b1, b2, b3;
            ldsm_x4_t(sb + OFF_WQ + (64 + (lane & 7)) * WQ_PITCH + (warp * 4 + (lane >> 3)) * 16, b0, b1, b2, b3);
            mma1688(cq[0], xa0[4], 0u, b0);
            mma1688(cq[1], xa0[4], 0u, b1);
            mma1688(cq[2], xa0[4], 0u, b2);
            mma1688(cq[3], xa0[4], 0u, b3);
            ldsm_x4_t(sb + OFF_W1 + (64 + (lane & 7)) * W1_PITCH + (ht0 + (lane >> 3)) * 16, b0, b1, b2, b3);
            mma1688(ch[0], xa0[4], 0u, b0);
            mma1688(ch[1], xa0[4], 0u, b1);
            mma1688(ch[2], xa0[4], 0u, b2);
            mma1688(ch[3], xa0[4], 0u, b3);
            if (has5) {
                ldsm_x1_t(sb + OFF_W1 + (64 + (lane & 7)) * W1_PITCH + (ht0 + 4) * 16, b0);
                mma1688(ch[4], xa0[4], 0u, b0);
            }
        }
        __syncwarp();
        if (lane == 0) mbar_arrive(bar0 + BAR_P1 * 8);
        if (g < 4) {
            float* dst = g_qh + ((size_t)(cta * 4 + g)) * 544;
#pragma unroll
            for (int j = 0; j < 4; j++)
                *reinterpret_cast<float2*>(dst + (warp * 4 + j) * 8 + 2 * t) = make_float2(cq[j][0], cq[j][1]);
#pragma unroll
            for (int j = 0; j < 5; j++)
                if (j < 4 || has5)
                    *reinterpret_cast<float2*>(dst + 256 + (ht0 + j) * 8 + 2 * t) = make_float2(ch[j][0], ch[j][1]);
        }
    }
    cbar();
    if (tid == 0) {
        __threadfence();
        asm volatile("st.release.gpu.global.u32 [%0], %1;" ::"l"(g_flag1 + cta), "r"(tag) : "memory");
    }
    if (warp == 0 && lane < 8) {
        unsigned it = 0, v;
        do {
            asm volatile("ld.acquire.gpu.global.u32 %0, [%1];" : "=r"(v) : "l"(g_flag1 + grp * 8 + lane) : "memory");
        } while (v != tag && ++it < SPIN_MAX);
    }
    cbar();
    {
        const float* src = g_qh + (size_t)(grp * 8) * 4 * 544;
        float qv[8];
        float4 hv[8], hw[8];
        const int i0 = tid, i1 = tid + 256;
        const int ho0 = (i0 / 72) * 544 + 256 + (i0 % 72) * 4;
        const int ho1 = (i1 / 72) * 544 + 256 + (i1 % 72) * 4;
#pragma unroll
        for (int s = 0; s < 8; s++) {
            qv[s] = __ldcg(src + (size_t)(s * 4 + bb) * 544 + tid);
            hv[s] = __ldcg(reinterpret_cast<const float4*>(src + (size_t)s * 4 * 544 + ho0));
            if (tid < 32) hw[s] = __ldcg(reinterpret_cast<const float4*>(src + (size_t)s * 4 * 544 + ho1));
        }
        float qs = 0.f;
#pragma unroll
        for (int s = 0; s < 8; s++) qs += qv[s];
        *reinterpret_cast<bf16*>(sp + OFF_Q + (tid >> 7) * 272 + (tid & 127) * 2) = __float2bfloat16_rn(qs);
        float4 a = make_float4(0.f, 0.f, 0.f, 0.f);
#pragma unroll
        for (int s = 0; s < 8; s++) { a.x += hv[s].x; a.y += hv[s].y; a.z += hv[s].z; a.w += hv[s].w; }
        {
            __nv_bfloat162 o0, o1;
            o0.x = __float2bfloat16_rn(silu_f(bfr(a.x))); o0.y = __float2bfloat16_rn(silu_f(bfr(a.y)));
            o1.x = __float2bfloat16_rn(silu_f(bfr(a.z))); o1.y = __float2bfloat16_rn(silu_f(bfr(a.w)));
            __nv_bfloat162* d = reinterpret_cast<__nv_bfloat162*>(sp + OFF_HS + (i0 / 72) * 592 + (i0 % 72) * 8);
            d[0] = o0; d[1] = o1;
        }
        if (tid < 32) {
            a = make_float4(0.f, 0.f, 0.f, 0.f);
#pragma unroll
            for (int s = 0; s < 8; s++) { a.x += hw[s].x; a.y += hw[s].y; a.z += hw[s].z; a.w += hw[s].w; }
            __nv_bfloat162 o0, o1;
            o0.x = __float2bfloat16_rn(silu_f(bfr(a.x))); o0.y = __float2bfloat16_rn(silu_f(bfr(a.y)));
            o1.x = __float2bfloat16_rn(silu_f(bfr(a.z))); o1.y = __float2bfloat16_rn(silu_f(bfr(a.w)));
            __nv_bfloat162* d = reinterpret_cast<__nv_bfloat162*>(sp + OFF_HS + (i1 / 72) * 592 + (i1 % 72) * 8);
            d[0] = o0; d[1] = o1;
        }
    }
    cbar();

    float sc[4][4];
    {
        uint32_t qb0[8], qb1[8];
#pragma unroll
        for (int ks = 0; ks < 8; ks++) {
            qb0[ks] = (g < 2) ? lds32(sb + OFF_Q + g * 272 + (ks * 16 + 2 * t) * 2) : 0u;
            qb1[ks] = (g < 2) ? lds32(sb + OFF_Q + g * 272 + (ks * 16 + 8 + 2 * t) * 2) : 0u;
        }
        const int mt = warp & 3, par = warp >> 2;
        const int krow = mt * 16 + (lane & 7) + ((lane >> 3) & 1) * 8;
        const int kc = lane >> 4;
#pragma unroll
        for (int i = 0; i < 4; i++) {
            const int s = par + 2 * i;
            float c0[4] = {0.f, 0.f, 0.f, 0.f}, c1[4] = {0.f, 0.f, 0.f, 0.f};
            mbar_wait(bar0 + (BAR_FULL + s) * 8, 0);
            const uint32_t base = sb + OFF_KV + s * STAGE_BYTES + krow * 128;
#pragma unroll
            for (int ks = 0; ks < 8; ks++) {
                uint32_t a0, a1, a2, a3;
                const int chunk = (ks & 3) * 2 + kc;
                ldsm_x4(base + (ks >> 2) * 8192 + ((chunk ^ (krow & 7)) << 4), a0, a1, a2, a3);
                if (ks & 1) mma16816(c1, a0, a1, a2, a3, qb0[ks], qb1[ks]);
                else mma16816(c0, a0, a1, a2, a3, qb0[ks], qb1[ks]);
            }
            __syncwarp();
            if (lane == 0) mbar_arrive(bar0 + (BAR_EMPTY + s) * 8);
#pragma unroll
            for (int j = 0; j < 4; j++) sc[i][j] = bfr(bfr(c0[j] + c1[j]) * 0.08838834764831845f);
        }
    }
    float mh0, mh1;
    {
        float m0 = -INFINITY, m1 = -INFINITY;
        if (t == 0) {
#pragma unroll
            for (int i = 0; i < 4; i++) {
                m0 = fmaxf(m0, fmaxf(sc[i][0], sc[i][2]));
                m1 = fmaxf(m1, fmaxf(sc[i][1], sc[i][3]));
            }
        }
#pragma unroll
        for (int o = 16; o > 0; o >>= 1) {
            m0 = fmaxf(m0, __shfl_xor_sync(0xffffffffu, m0, o));
            m1 = fmaxf(m1, __shfl_xor_sync(0xffffffffu, m1, o));
        }
        float* wmax = reinterpret_cast<float*>(sp + OFF_WMAX);
        if (lane == 0) { wmax[warp * 2] = m0; wmax[warp * 2 + 1] = m1; }
        cbar();
        m0 = wmax[0]; m1 = wmax[1];
#pragma unroll
        for (int w = 1; w < 8; w++) { m0 = fmaxf(m0, wmax[w * 2]); m1 = fmaxf(m1, wmax[w * 2 + 1]); }
        mh0 = m0; mh1 = m1;
        float s0 = 0.f, s1 = 0.f;
        if (t == 0) {
            const int mt = warp & 3, par = warp >> 2;
            bf16* ps = reinterpret_cast<bf16*>(sp + OFF_P);
#pragma unroll
            for (int i = 0; i < 4; i++) {
                const int key = (par + 2 * i) * 64 + mt * 16 + g;
                bf16 p00 = __float2bfloat16_rn(__expf(sc[i][0] - m0));
                bf16 p01 = __float2bfloat16_rn(__expf(sc[i][1] - m1));
                bf16 p10 = __float2bfloat16_rn(__expf(sc[i][2] - m0));
                bf16 p11 = __float2bfloat16_rn(__expf(sc[i][3] - m1));
                ps[key] = p00; ps[520 + key] = p01; ps[key + 8] = p10; ps[520 + key + 8] = p11;
                s0 += __bfloat162float(p00) + __bfloat162float(p10);
                s1 += __bfloat162float(p01) + __bfloat162float(p11);
            }
        }
#pragma unroll
        for (int o = 16; o > 0; o >>= 1) {
            s0 += __shfl_xor_sync(0xffffffffu, s0, o);
            s1 += __shfl_xor_sync(0xffffffffu, s1, o);
        }
        float* wsum = reinterpret_cast<float*>(sp + OFF_WSUM);
        if (lane == 0) { wsum[warp * 2] = s0; wsum[warp * 2 + 1] = s1; }
        cbar();
    }
    {
        float c0[4] = {0.f, 0.f, 0.f, 0.f}, c1[4] = {0.f, 0.f, 0.f, 0.f};
        const int vrow = (lane & 7) + (lane >> 4) * 8;
        const int chunk = (warp & 3) * 2 + ((lane >> 3) & 1);
        const uint32_t hoff = (warp >> 2) * 8192;
#pragma unroll 1
        for (int s = 0; s < NSTAGE; s++) {
            mbar_wait(bar0 + (BAR_FULL + s) * 8, 1);
            const uint32_t base = sb + OFF_KV + s * STAGE_BYTES + hoff;
#pragma unroll
            for (int ks = 0; ks < 4; ks++) {
                uint32_t a0, a1, a2, a3;
                const int row = ks * 16 + vrow;
                ldsm_x4_t(base + row * 128 + ((chunk ^ (row & 7)) << 4), a0, a1, a2, a3);
                uint32_t b0 = (g < 2) ? lds32(sb + OFF_P + g * 1040 + (s * 64 + ks * 16 + 2 * t) * 2) : 0u;
                uint32_t b1 = (g < 2) ? lds32(sb + OFF_P + g * 1040 + (s * 64 + ks * 16 + 8 + 2 * t) * 2) : 0u;
                if (ks & 1) mma16816(c1, a0, a1, a2, a3, b0, b1);
                else mma16816(c0, a0, a1, a2, a3, b0, b1);
            }
        }
        uint2* dst = g_o + (size_t)cta * 264;
        if (t == 0) {
            const int d = warp * 16 + g;
            st_ll(dst + d, c0[0] + c1[0], tag);
            st_ll(dst + 128 + d, c0[1] + c1[1], tag);
            st_ll(dst + d + 8, c0[2] + c1[2], tag);
            st_ll(dst + 128 + d + 8, c0[3] + c1[3], tag);
        }
        if (tid == 1) {
            const float* wsum = reinterpret_cast<const float*>(sp + OFF_WSUM);
            float l0 = 0.f, l1 = 0.f;
#pragma unroll
            for (int w = 0; w < 8; w++) { l0 += wsum[w * 2]; l1 += wsum[w * 2 + 1]; }
            st_ll(dst + 256, mh0, tag);
            st_ll(dst + 257, mh1, tag);
            st_ll(dst + 258, l0, tag);
            st_ll(dst + 259, l1, tag);
        }
    }
    {
        const uint2* src = g_o + (size_t)(grp * 8) * 264;
        if (warp == 0) {
            uint2 v;
            unsigned it = 0;
            do { v = ld_ll(src + (lane >> 2) * 264 + 256 + (lane & 3)); } while (v.y != tag && ++it < SPIN_MAX);
            const float val = __uint_as_float(v.x);
            const int hd = lane & 1;
            const int sbase = (lane >> 3) * 8;
            const float m0 = __shfl_sync(0xffffffffu, val, sbase + hd);
            const float l0 = __shfl_sync(0xffffffffu, val, sbase + 2 + hd);
            const float m1 = __shfl_sync(0xffffffffu, val, sbase + 4 + hd);
            const float l1 = __shfl_sync(0xffffffffu, val, sbase + 6 + hd);
            const float M = fmaxf(m0, m1);
            const float e0 = __expf(m0 - M), e1 = __expf(m1 - M);
            const float inv = 1.0f / (l0 * e0 + l1 * e1);
            if ((lane & 2) == 0) {
                float* cw = reinterpret_cast<float*>(sp + OFF_CW);
                cw[(lane >> 2) * 2 + hd] = ((lane >> 2) & 1) ? e1 * inv : e0 * inv;
            }
        }
        uint2 v[8];
        unsigned it = 0;
        bool ok;
        do {
            ok = true;
#pragma unroll
            for (int s = 0; s < 8; s++) v[s] = ld_ll(src + s * 264 + tid);
#pragma unroll
            for (int s = 0; s < 8; s++) ok = ok && (v[s].y == tag);
        } while (!ok && ++it < SPIN_MAX);
        cbar();
        const float* cw = reinterpret_cast<const float*>(sp + OFF_CW);
        const int hd = tid >> 7;
#pragma unroll
        for (int b = 0; b < 4; b++) {
            float o = __uint_as_float(v[2 * b].x) * cw[(2 * b) * 2 + hd] + __uint_as_float(v[2 * b + 1].x) * cw[(2 * b + 1) * 2 + hd];
            *reinterpret_cast<bf16*>(sp + OFF_OS + b * 528 + tid * 2) = __float2bfloat16_rn(o);
        }
        cbar();
    }
    {
        const int lrow = (lane & 7) + ((lane >> 3) & 1) * 8;
        const int ltile = lane >> 4;
        float* red = reinterpret_cast<float*>(sp + OFF_RED);
        {
            float c[9][4];
#pragma unroll
            for (int j = 0; j < 9; j++)
#pragma unroll
                for (int i = 0; i < 4; i++) c[j][i] = 0.f;
            mbar_wait(bar0 + BAR_WO * 8, 0);
#pragma unroll
            for (int kk = 0; kk < 2; kk++) {
                const int ks = warp * 2 + kk;
                const uint32_t a0 = (g < 4) ? lds32(sb + OFF_OS + g * 528 + (ks * 16 + 2 * t) * 2) : 0u;
                const uint32_t a2 = (g < 4) ? lds32(sb + OFF_OS + g * 528 + (ks * 16 + 8 + 2 * t) * 2) : 0u;
                const uint32_t base = sb + OFF_WO + (ks * 16 + lrow) * WO_PITCH;
#pragma unroll
                for (int jp = 0; jp < 4; jp++) {
                    uint32_t b0, b1, b2, b3;
                    ldsm_x4_t(base + (jp * 2 + ltile) * 16, b0, b1, b2, b3);
                    mma16816(c[jp * 2], a0, 0u, a2, 0u, b0, b1);
                    mma16816(c[jp * 2 + 1], a0, 0u, a2, 0u, b2, b3);
                }
                uint32_t b0, b1;
                ldsm_x2_t(base + 8 * 16, b0, b1);
                mma16816(c[8], a0, 0u, a2, 0u, b0, b1);
            }
            if (g < 4) {
#pragma unroll
                for (int j = 0; j < 9; j++)
                    *reinterpret_cast<float2*>(red + ((warp * 2 + 0) * 4 + g) * 72 + j * 8 + 2 * t) = make_float2(c[j][0], c[j][1]);
            }
        }
        {
            float c[9][4];
#pragma unroll
            for (int j = 0; j < 9; j++)
#pragma unroll
                for (int i = 0; i < 4; i++) c[j][i] = 0.f;
#pragma unroll
            for (int ci = 0; ci < 3; ci++) {
                const int wk = (warp + ci * 2) & 7;
                if (wk < 6) {
                    mbar_wait(bar0 + (BAR_W2 + ci) * 8, 0);
                    const int ks = ci * 6 + wk;
                    const uint32_t a0 = (g < 4) ? lds32(sb + OFF_HS + g * 592 + (ks * 16 + 2 * t) * 2) : 0u;
                    const uint32_t a2 = (g < 4) ? lds32(sb + OFF_HS + g * 592 + (ks * 16 + 8 + 2 * t) * 2) : 0u;
                    const uint32_t base = sb + OFF_W2 + (ks * 16 + lrow) * WO_PITCH;
#pragma unroll
                    for (int jp = 0; jp < 4; jp++) {
                        uint32_t b0, b1, b2, b3;
                        ldsm_x4_t(base + (jp * 2 + ltile) * 16, b0, b1, b2, b3);
                        mma16816(c[jp * 2], a0, 0u, a2, 0u, b0, b1);
                        mma16816(c[jp * 2 + 1], a0, 0u, a2, 0u, b2, b3);
                    }
                    uint32_t b0, b1;
                    ldsm_x2_t(base + 8 * 16, b0, b1);
                    mma16816(c[8], a0, 0u, a2, 0u, b0, b1);
                }
            }
            if (g < 4) {
#pragma unroll
                for (int j = 0; j < 9; j++)
                    *reinterpret_cast<float2*>(red + ((warp * 2 + 1) * 4 + g) * 72 + j * 8 + 2 * t) = make_float2(c[j][0], c[j][1]);
            }
        }
        cbar();
#pragma unroll
        for (int k = 0; k < 3; k++) {
            const int vi = tid + k * 256;
            if (vi < 576) {
                float a = 0.f;
#pragma unroll
                for (int w = 0; w < 8; w++) a += red[w * 576 + vi];
                const int which = vi / 288;
                const int el = vi - which * 288;
                const int dg = el / 18, e = el - dg * 18;
                st_ll(g_fin + ((size_t)((r * 16 + dg) * 18 + e) * 2 + which) * 16 + grp, a, tag);
            }
        }
    }
    {
#pragma unroll
        for (int k = 0; k < 3; k++) {
            const int e = warp + k * 8;
            if (e < 18) {
                const int el = grp * 18 + e;
                const int b = el / 72, c = el - b * 72;
                const int oi = b * DM + r * 72 + c;
                const float xv = __bfloat162float(x[oi]);
                const uint2* src = g_fin + ((size_t)((r * 16 + grp) * 18 + e) * 2) * 16 + lane;
                uint2 v;
                unsigned it = 0;
                do { v = ld_ll(src); } while (v.y != tag && ++it < SPIN_MAX);
                float a = __uint_as_float(v.x);
#pragma unroll
                for (int o = 8; o > 0; o >>= 1) a += __shfl_xor_sync(0xffffffffu, a, o);
                const float ov = __shfl_sync(0xffffffffu, a, 16);
                if (lane == 0) {
                    const float sv = bfr(a);
                    const float gv = bfr(silu_f(bfr(ov)));
                    out[oi] = __float2bfloat16_rn(xv + bfr(sv * gv));
                }
            }
        }
    }
    if (tid == 0) g_epoch[cta] = tag;
}

typedef CUresult (*PFN_encodeTiled)(CUtensorMap*, CUtensorMapDataType, cuuint32_t, void*, const cuuint64_t*,
                                    const cuuint64_t*, const cuuint32_t*, const cuuint32_t*, CUtensorMapInterleave,
                                    CUtensorMapSwizzle, CUtensorMapL2promotion, CUtensorMapFloatOOBfill);

void make_map(PFN_encodeTiled fn, CUtensorMap* m, const void* ptr, uint64_t cols, uint64_t rows, uint32_t bc, uint32_t br,
              CUtensorMapSwizzle sw) {
    cuuint64_t dims[2] = {cols, rows};
    cuuint64_t strides[1] = {cols * 2};
    cuuint32_t box[2] = {bc, br};
    cuuint32_t es[2] = {1, 1};
    fn(m, CU_TENSOR_MAP_DATA_TYPE_BFLOAT16, 2, const_cast<void*>(ptr), dims, strides, box, es,
       CU_TENSOR_MAP_INTERLEAVE_NONE, sw, CU_TENSOR_MAP_L2_PROMOTION_L2_256B, CU_TENSOR_MAP_FLOAT_OOB_FILL_NONE);
}

}

extern "C" void kernel_launch(void* const* d_in, const int* in_sizes, int n_in, void* d_out, int out_size) {
    const bf16* x = (const bf16*)d_in[0];
    const bf16* kc = (const bf16*)d_in[1];
    const bf16* vc = (const bf16*)d_in[2];
    const bf16* wq = (const bf16*)d_in[3];
    const bf16* wo = (const bf16*)d_in[4];
    const bf16* w1 = (const bf16*)d_in[6];
    const bf16* w2 = (const bf16*)d_in[7];

    static PFN_encodeTiled fn = nullptr;
    if (!fn) {
        void* p = nullptr;
        cudaDriverEntryPointQueryResult qr;
        cudaGetDriverEntryPoint("cuTensorMapEncodeTiled", &p, cudaEnableDefault, &qr);
        fn = (PFN_encodeTiled)p;
        cudaFuncSetAttribute(fused_decode_kernel, cudaFuncAttributeMaxDynamicSharedMemorySize, SMEM_BYTES);
    }
    CUtensorMap tmK, tmV, tmWo, tmW2;
    make_map(fn, &tmK, kc, DH, (uint64_t)4 * HKV * SK, 64, 64, CU_TENSOR_MAP_SWIZZLE_128B);
    make_map(fn, &tmV, vc, DH, (uint64_t)4 * HKV * SK, 64, 64, CU_TENSOR_MAP_SWIZZLE_128B);
    make_map(fn, &tmWo, wo, DM, 4096, 72, 256, CU_TENSOR_MAP_SWIZZLE_NONE);
    make_map(fn, &tmW2, w2, DM, FF, 72, 96, CU_TENSOR_MAP_SWIZZLE_NONE);
    fused_decode_kernel<<<NCTA, NTHREADS, SMEM_BYTES>>>(tmK, tmV, tmWo, tmW2, x, wq, w1, (bf16*)d_out);
}
```

```cpp
#include <cuda_runtime.h>
#include <cuda_bf16.h>
#include <cuda.h>
#include <stdint.h>

typedef __nv_bfloat16 bf16;

namespace {

constexpr int DM = 576;
constexpr int HKV = 16;
constexpr int SK = 4096;
constexpr int DH = 128;
constexpr int WIN = 1024;
constexpr int FF = 4608;
constexpr int NCTA = 128;
constexpr int NTHREADS = 288;

constexpr int KROWS = 72;
constexpr int W1_PITCH = 144;
constexpr int WO_PITCH = 80;
constexpr int SLOT_BYTES = 16384;
#define NSLOT_ 5
#define WIN_S 2
#define PACE_NS 670
#define PACE_END 28
#define HG0 1
#define HG1 4
#define PACE_OFF 0
constexpr int NSLOT = NSLOT_;
constexpr int IT_WQ = 0, IT_W1 = 3, IT_K = 6, IT_V = 14, IT_W2 = 22, IT_WO = 25, NITEM = 28;

constexpr int HS_PITCH = 1168;
constexpr int OS_PITCH = 1040;
constexpr int OFF_RING = 0;
constexpr int OFF_QBUF = NSLOT * SLOT_BYTES;
constexpr int OFF_HBUF = OFF_QBUF + 8 * 256 * 4;
constexpr int OFF_OBUF = OFF_HBUF + 8 * 144 * 4;
constexpr int OFF_FBUF = OFF_OBUF + 132 * 4;
constexpr int OFF_HS = OFF_FBUF + 8 * 36 * 4;
constexpr int OFF_OS = OFF_HS + 4 * HS_PITCH;
constexpr int OFF_P = OFF_OS + 4 * OS_PITCH;
constexpr int OFF_Q = OFF_P + 2 * 520 * 2;
constexpr int OFF_XN = OFF_Q + 2 * 136 * 2;
constexpr int OFF_WMAX = OFF_XN + 4 * 80 * 2;
constexpr int OFF_WSUM = OFF_WMAX + 64;
constexpr int OFF_BAR = OFF_WSUM + 64;
constexpr int OFF_END = OFF_BAR + 16 * 8;
constexpr int OFF_RED = OFF_QBUF;
constexpr int SMEM_BYTES = OFF_END + 1024;
static_assert(OFF_BAR % 8 == 0, "bar align");
static_assert(OFF_OBUF % 16 == 0 && OFF_HBUF % 16 == 0 && OFF_HS % 16 == 0 && OFF_WMAX % 16 == 0 && OFF_OS % 16 == 0, "align");
static_assert(8 * 320 * 4 <= 8 * 256 * 4 + 8 * 144 * 4, "red fits");
static_assert(SMEM_BYTES <= 115712, "smem");

constexpr int BAR_FULL = 0;
constexpr int BAR_EMPTY = 5;
constexpr int BAR_Q = 10;
constexpr int BAR_H1 = 11;
constexpr int BAR_O = 12;
constexpr int BAR_F = 13;

constexpr unsigned SPIN_MAX = 1u << 17;

__device__ uint2 g_o[16 * 4 * 128];
__device__ uint2 g_h[16 * 4 * 144];
__device__ unsigned g_epoch[NCTA];
#define TL(i)
#define TLP(i)

__device__ __forceinline__ void mbar_init(uint32_t bar, uint32_t cnt) {
    asm volatile("mbarrier.init.shared::cta.b64 [%0], %1;" ::"r"(bar), "r"(cnt) : "memory");
}
__device__ __forceinline__ void mbar_expect_tx(uint32_t bar, uint32_t bytes) {
    asm volatile("mbarrier.arrive.expect_tx.shared::cta.b64 _, [%0], %1;" ::"r"(bar), "r"(bytes) : "memory");
}
__device__ __forceinline__ void mbar_arrive(uint32_t bar) {
    asm volatile("mbarrier.arrive.shared::cta.b64 _, [%0];" ::"r"(bar) : "memory");
}
__device__ __forceinline__ void mbar_wait(uint32_t bar, uint32_t parity) {
    unsigned it = 0;
    uint32_t ok;
    do {
        asm volatile(
            "{\n.reg .pred p;\n"
            "mbarrier.try_wait.parity.shared::cta.b64 p, [%1], %2;\n"
            "selp.u32 %0, 1, 0, p;\n}\n"
            : "=r"(ok)
            : "r"(bar), "r"(parity)
            : "memory");
    } while (!ok && ++it < SPIN_MAX);
}
__device__ __forceinline__ void mbar_wait_cluster(uint32_t bar, uint32_t parity) {
    unsigned it = 0;
    uint32_t ok;
    do {
        asm volatile(
            "{\n.reg .pred p;\n"
            "mbarrier.try_wait.parity.acquire.cluster.shared::cta.b64 p, [%1], %2;\n"
            "selp.u32 %0, 1, 0, p;\n}\n"
            : "=r"(ok)
            : "r"(bar), "r"(parity)
            : "memory");
    } while (!ok && ++it < SPIN_MAX);
}
__device__ __forceinline__ uint32_t mapa(uint32_t addr, uint32_t rank) {
    uint32_t r;
    asm("mapa.shared::cluster.u32 %0, %1, %2;" : "=r"(r) : "r"(addr), "r"(rank));
    return r;
}
__device__ __forceinline__ void st_async_v2(uint32_t raddr, float a, float b, uint32_t rbar) {
    asm volatile("st.async.shared::cluster.mbarrier::complete_tx::bytes.v2.f32 [%0], {%1,%2}, [%3];" ::"r"(raddr), "f"(a),
                 "f"(b), "r"(rbar)
                 : "memory");
}
__device__ __forceinline__ void st_async_b32(uint32_t raddr, uint32_t a, uint32_t rbar) {
    asm volatile("st.async.shared::cluster.mbarrier::complete_tx::bytes.b32 [%0], %1, [%2];" ::"r"(raddr), "r"(a), "r"(rbar)
                 : "memory");
}
__device__ __forceinline__ void tma_2d(uint32_t dst, const CUtensorMap* tm, int c0, int c1, uint32_t bar) {
    asm volatile(
        "cp.async.bulk.tensor.2d.shared::cluster.global.mbarrier::complete_tx::bytes [%0], [%1, {%3, %4}], [%2];" ::"r"(dst),
        "l"(tm), "r"(bar), "r"(c0), "r"(c1)
        : "memory");
}
__device__ __forceinline__ void tma_3d(uint32_t dst, const CUtensorMap* tm, int c0, int c1, int c2, uint32_t bar) {
    asm volatile(
        "cp.async.bulk.tensor.3d.shared::cluster.global.mbarrier::complete_tx::bytes [%0], [%1, {%3, %4, %5}], [%2];" ::"r"(dst),
        "l"(tm), "r"(bar), "r"(c0), "r"(c1), "r"(c2)
        : "memory");
}
__device__ __forceinline__ void ldsm_x4(uint32_t addr, uint32_t& r0, uint32_t& r1, uint32_t& r2, uint32_t& r3) {
    asm volatile("ldmatrix.sync.aligned.m8n8.x4.shared.b16 {%0,%1,%2,%3}, [%4];"
                 : "=r"(r0), "=r"(r1), "=r"(r2), "=r"(r3)
                 : "r"(addr)
                 : "memory");
}
__device__ __forceinline__ void ldsm_x4_t(uint32_t addr, uint32_t& r0, uint32_t& r1, uint32_t& r2, uint32_t& r3) {
    asm volatile("ldmatrix.sync.aligned.m8n8.x4.trans.shared.b16 {%0,%1,%2,%3}, [%4];"
                 : "=r"(r0), "=r"(r1), "=r"(r2), "=r"(r3)
                 : "r"(addr)
                 : "memory");
}
__device__ __forceinline__ void ldsm_x2_t(uint32_t addr, uint32_t& r0, uint32_t& r1) {
    asm volatile("ldmatrix.sync.aligned.m8n8.x2.trans.shared.b16 {%0,%1}, [%2];"
                 : "=r"(r0), "=r"(r1)
                 : "r"(addr)
                 : "memory");
}
__device__ __forceinline__ void ldsm_x1_t(uint32_t addr, uint32_t& r0) {
    asm volatile("ldmatrix.sync.aligned.m8n8.x1.trans.shared.b16 {%0}, [%1];" : "=r"(r0) : "r"(addr) : "memory");
}
__device__ __forceinline__ void mma16816(float (&c)[4], uint32_t a0, uint32_t a1, uint32_t a2, uint32_t a3, uint32_t b0,
                                         uint32_t b1) {
    asm volatile(
        "mma.sync.aligned.m16n8k16.row.col.f32.bf16.bf16.f32 {%0,%1,%2,%3}, {%4,%5,%6,%7}, {%8,%9}, {%0,%1,%2,%3};"
        : "+f"(c[0]), "+f"(c[1]), "+f"(c[2]), "+f"(c[3])
        : "r"(a0), "r"(a1), "r"(a2), "r"(a3), "r"(b0), "r"(b1));
}
__device__ __forceinline__ void mma1688(float (&c)[4], uint32_t a0, uint32_t a1, uint32_t b0) {
    asm volatile("mma.sync.aligned.m16n8k8.row.col.f32.bf16.bf16.f32 {%0,%1,%2,%3}, {%4,%5}, {%6}, {%0,%1,%2,%3};"
                 : "+f"(c[0]), "+f"(c[1]), "+f"(c[2]), "+f"(c[3])
                 : "r"(a0), "r"(a1), "r"(b0));
}
__device__ __forceinline__ void cbar() { asm volatile("bar.sync 1, 256;" ::: "memory"); }
__device__ __forceinline__ float bfr(float v) { return __bfloat162float(__float2bfloat16_rn(v)); }
__device__ __forceinline__ uint32_t lds32(uint32_t addr) {
    uint32_t v;
    asm volatile("ld.shared.b32 %0, [%1];" : "=r"(v) : "r"(addr) : "memory");
    return v;
}
__device__ __forceinline__ uint4 ld_ll2(const uint2* p) {
    uint4 v;
    asm volatile("ld.relaxed.gpu.global.v4.u32 {%0,%1,%2,%3}, [%4];" : "=r"(v.x), "=r"(v.y), "=r"(v.z), "=r"(v.w) : "l"(p) : "memory");
    return v;
}
__device__ __forceinline__ void st_ll(uint2* p, uint32_t val, unsigned tag) {
    asm volatile("st.relaxed.gpu.global.v2.u32 [%0], {%1,%2};" ::"l"(p), "r"(val), "r"(tag) : "memory");
}
__device__ __forceinline__ float silu_f(float v) { return __fdividef(v, 1.0f + __expf(-v)); }
__device__ __forceinline__ float4 lds128(uint32_t addr) {
    float4 v;
    asm volatile("ld.shared.v4.f32 {%0,%1,%2,%3}, [%4];" : "=f"(v.x), "=f"(v.y), "=f"(v.z), "=f"(v.w) : "r"(addr) : "memory");
    return v;
}
__device__ __forceinline__ uint32_t pack_bf16(float a, float b) {
    __nv_bfloat162 o;
    o.x = __float2bfloat16_rn(a);
    o.y = __float2bfloat16_rn(b);
    return *reinterpret_cast<uint32_t*>(&o);
}

__global__ void __launch_bounds__(NTHREADS, 2)
fused_decode_kernel(const __grid_constant__ CUtensorMap tmWq, const __grid_constant__ CUtensorMap tmK,
                    const __grid_constant__ CUtensorMap tmW1, const __grid_constant__ CUtensorMap tmV,
                    const __grid_constant__ CUtensorMap tmWo, const __grid_constant__ CUtensorMap tmW2,
                    const bf16* __restrict__ x, bf16* __restrict__ out) {
    extern __shared__ uint8_t smem_raw[];
    const uint32_t sb = (((uint32_t)__cvta_generic_to_shared(smem_raw)) + 1023u) & ~1023u;
    uint8_t* sp = smem_raw + (sb - (uint32_t)__cvta_generic_to_shared(smem_raw));

    const int tid = threadIdx.x;
    const int warp = tid >> 5;
    const int lane = tid & 31;
    const int cta = blockIdx.x;
    const int grp = cta >> 3;
    const int r = cta & 7;
    const int bb = r >> 1;
    const int split = r & 1;
    const uint32_t bar0 = sb + OFF_BAR;
    TL(14);

    if (warp == 8) {
        TLP(16);
        unsigned long long tstart;
        asm volatile("mov.u64 %0, %globaltimer;" : "=l"(tstart));
        const int row0 = (bb * HKV + grp) * SK + (SK - WIN) + split * 512;
        const int col0 = grp * 36 - 4 * (grp & 1);
        if (lane == 0) {
            for (int i = 0; i < NSLOT; i++) {
                mbar_init(bar0 + (BAR_FULL + i) * 8, 1);
                mbar_init(bar0 + (BAR_EMPTY + i) * 8, 8);
            }
            mbar_init(bar0 + BAR_Q * 8, 1);
            mbar_init(bar0 + BAR_H1 * 8, 1);
            mbar_init(bar0 + BAR_O * 8, 1);
            mbar_init(bar0 + BAR_F * 8, 1);
            asm volatile("fence.mbarrier_init.release.cluster;" ::: "memory");
            asm volatile("fence.proxy.async.shared::cta;" ::: "memory");
            TLP(17);
            for (int i = 0; i < 3; i++) {
                mbar_expect_tx(bar0 + (BAR_FULL + i) * 8, 24 * 512);
                tma_3d(sb + OFF_RING + i * SLOT_BYTES, &tmWq, 0, r * KROWS + i * 24, grp * 4, bar0 + (BAR_FULL + i) * 8);
            }
            TLP(18);
            for (int it = IT_W1; it < NSLOT; it++) {
                mbar_expect_tx(bar0 + (BAR_FULL + it) * 8, 24 * 576);
                tma_3d(sb + OFF_RING + it * SLOT_BYTES, &tmW1, 0, r * KROWS + (it - IT_W1) * 24, grp * 4,
                       bar0 + (BAR_FULL + it) * 8);
            }
            mbar_expect_tx(bar0 + BAR_Q * 8, 8 * 1024);
            mbar_expect_tx(bar0 + BAR_H1 * 8, 8 * 576);
            mbar_expect_tx(bar0 + BAR_O * 8, 130 * 4);
            mbar_expect_tx(bar0 + BAR_F * 8, 8 * 144);
            TLP(15);
            asm volatile("prefetch.tensormap [%0];" ::"l"(&tmK) : "memory");
            asm volatile("prefetch.tensormap [%0];" ::"l"(&tmV) : "memory");
            asm volatile("prefetch.tensormap [%0];" ::"l"(&tmWo) : "memory");
            asm volatile("prefetch.tensormap [%0];" ::"l"(&tmW2) : "memory");
        }
        TLP(19);
        __syncthreads();
        TLP(20);
        asm volatile("barrier.cluster.arrive.relaxed.aligned;" ::: "memory");
        TLP(21);
        if (lane == 0) {
#pragma unroll 1
            for (int it = NSLOT; it < NITEM; it++) {
                const int sl = it % NSLOT;
                const uint32_t fb = bar0 + (BAR_FULL + sl) * 8;
                const uint32_t dst = sb + OFF_RING + sl * SLOT_BYTES;
                mbar_wait(bar0 + (BAR_EMPTY + sl) * 8, ((it / NSLOT) - 1) & 1);
                {
                    unsigned long long now;
                    asm volatile("mov.u64 %0, %globaltimer;" : "=l"(now));
                    const int pit = it - WIN_S;
                    if (it < PACE_END && (unsigned)(now - tstart) < (unsigned)(PACE_NS * (it - 2) + PACE_OFF))
                        mbar_wait(bar0 + (BAR_FULL + pit % NSLOT) * 8, (pit / NSLOT) & 1);
                }
                if (it < IT_K) {
                    mbar_expect_tx(fb, 24 * 576);
                    tma_3d(dst, &tmW1, 0, r * KROWS + (it - IT_W1) * 24, grp * 4, fb);
                } else if (it < IT_V) {
                    const int s = it - IT_K;
                    mbar_expect_tx(fb, SLOT_BYTES);
                    tma_3d(dst, &tmK, 0, row0 + s * 64, 0, fb);
                } else if (it < IT_W2) {
                    const int s = it - IT_V;
                    mbar_expect_tx(fb, SLOT_BYTES);
                    tma_3d(dst, &tmV, 0, row0 + s * 64, 0, fb);
                } else if (it < IT_WO) {
                    const int i = it - IT_W2;
                    mbar_expect_tx(fb, 192 * WO_PITCH);
                    for (int j = 0; j < 3; j++)
                        tma_2d(dst + j * 64 * WO_PITCH, &tmW2, col0, r * 576 + i * 192 + j * 64, fb);
                } else {
                    const int i = it - IT_WO;
                    const int nb = (i < 2) ? 3 : 2;
                    mbar_expect_tx(fb, nb * 64 * WO_PITCH);
                    for (int j = 0; j < nb; j++)
                        tma_2d(dst + j * 64 * WO_PITCH, &tmWo, col0, r * 512 + i * 192 + j * 64, fb);
                }
            }
        }
        __syncwarp();
        asm volatile("barrier.cluster.wait.acquire.aligned;" ::: "memory");
        return;
    }

    const unsigned tag = g_epoch[cta] + 1u;
    uint32_t xu[9];
    if (warp < 4) {
        const uint32_t* xr = reinterpret_cast<const uint32_t*>(x + warp * DM);
#pragma unroll
        for (int i = 0; i < 9; i++) xu[i] = xr[lane + 32 * i];
    }
    int xoi = 0;
    float xres = 0.f;
    if (tid < 18) {
        const int el = r * 18 + tid;
        const int b = el / 36, c = el - b * 36;
        xoi = b * DM + grp * 36 + c;
        xres = __bfloat162float(x[xoi]);
    }
    __syncthreads();
    asm volatile("barrier.cluster.arrive.relaxed.aligned;" ::: "memory");
    const int g = lane >> 2;
    const int t = lane & 3;
    TL(0);

#define ITEM_WAIT(it) mbar_wait(bar0 + (BAR_FULL + (it) % NSLOT) * 8, ((it) / NSLOT) & 1)
#define ITEM_DONE(it) do { __syncwarp(); if (lane == 0) mbar_arrive(bar0 + (BAR_EMPTY + (it) % NSLOT) * 8); } while (0)
#define ITEM_ADDR(it) (sb + OFF_RING + ((it) % NSLOT) * SLOT_BYTES)

    if (warp < 4) {
        float v0[9], v1[9];
        float sum = 0.f;
#pragma unroll
        for (int i = 0; i < 9; i++) {
            uint32_t u = xu[i];
            v0[i] = __uint_as_float(u << 16);
            v1[i] = __uint_as_float(u & 0xffff0000u);
            sum += v0[i] + v1[i];
        }
#pragma unroll
        for (int o = 16; o > 0; o >>= 1) sum += __shfl_xor_sync(0xffffffffu, sum, o);
        const float mean = sum * (1.0f / DM);
        float sq = 0.f;
#pragma unroll
        for (int i = 0; i < 9; i++) {
            float a = v0[i] - mean, c = v1[i] - mean;
            sq += a * a + c * c;
        }
#pragma unroll
        for (int o = 16; o > 0; o >>= 1) sq += __shfl_xor_sync(0xffffffffu, sq, o);
        const float mb = bfr(mean);
        const float vb = bfr(sq * (1.0f / DM));
        const float rden = 1.0f / bfr(sqrtf(bfr(vb + 1e-5f)));
#pragma unroll
        for (int i = 0; i < 9; i++) {
            int pi = lane + 32 * i - r * 36;
            if (pi >= 0 && pi < 36)
                *reinterpret_cast<uint32_t*>(sp + OFF_XN + warp * 160 + pi * 4) =
                    pack_bf16(bfr(v0[i] - mb) * rden, bfr(v1[i] - mb) * rden);
        }
    }
    cbar();
    TL(1);

    uint32_t xa[9];
#pragma unroll
    for (int i = 0; i < 9; i++) xa[i] = (g < 4) ? lds32(sb + OFF_XN + g * 160 + (i * 8 + 2 * t) * 2) : 0u;
    const int lrow = (lane & 7) + ((lane >> 3) & 1) * 8;
    const int ltile = lane >> 4;

    {
        float cq[4][4];
#pragma unroll
        for (int j = 0; j < 4; j++)
#pragma unroll
            for (int i = 0; i < 4; i++) cq[j][i] = 0.f;
#pragma unroll
        for (int i = 0; i < 3; i++) {
            ITEM_WAIT(IT_WQ + i);
            const uint32_t base = ITEM_ADDR(IT_WQ + i);
            uint32_t b0, b1, b2, b3;
#pragma unroll
            for (int jp = 0; jp < 2; jp++) {
                ldsm_x4_t(base + (warp >> 1) * 3072 + lrow * 128 + ((((warp & 1) * 4 + jp * 2 + ltile) ^ (lrow & 7)) << 4), b0, b1, b2, b3);
                mma16816(cq[jp * 2], xa[i * 3], 0u, xa[i * 3 + 1], 0u, b0, b1);
                mma16816(cq[jp * 2 + 1], xa[i * 3], 0u, xa[i * 3 + 1], 0u, b2, b3);
            }
            ldsm_x4_t(base + (warp >> 1) * 3072 + (16 + (lane & 7)) * 128 + ((((warp & 1) * 4 + (lane >> 3)) ^ (lane & 7)) << 4), b0, b1, b2, b3);
            mma1688(cq[0], xa[i * 3 + 2], 0u, b0);
            mma1688(cq[1], xa[i * 3 + 2], 0u, b1);
            mma1688(cq[2], xa[i * 3 + 2], 0u, b2);
            mma1688(cq[3], xa[i * 3 + 2], 0u, b3);
            ITEM_DONE(IT_WQ + i);
        }
        TL(2);
        asm volatile("barrier.cluster.wait.acquire.aligned;" ::: "memory");
        if (g < 4) {
#pragma unroll
            for (int d = 0; d < 2; d++) {
                const uint32_t ra = mapa(sb + OFF_QBUF + r * 1024 + (warp * 32 + 2 * t) * 4, 2 * g + d);
                const uint32_t rb = mapa(bar0 + BAR_Q * 8, 2 * g + d);
#pragma unroll
                for (int j = 0; j < 4; j++) st_async_v2(ra + j * 32, cq[j][0], cq[j][1], rb);
            }
        }
    }
    TL(3);
    {
        float ch[5][4];
#pragma unroll
        for (int j = 0; j < 5; j++)
#pragma unroll
            for (int i = 0; i < 4; i++) ch[j][i] = 0.f;
        const int ht0 = (warp < 4) ? warp * 5 : 20 + (warp - 4) * 4;
        const bool has5 = warp < 4;
#define W1_TILE(nt) (((nt) / 9) * 3456 + ((nt) % 9) * 16)
        const uint32_t w1o0 = W1_TILE(ht0 + ltile), w1o1 = W1_TILE(ht0 + 2 + ltile), w1o2 = W1_TILE(ht0 + (lane >> 3)),
                       w1o3 = W1_TILE(ht0 + 4);
#pragma unroll
        for (int i = 0; i < 3; i++) {
            ITEM_WAIT(IT_W1 + i);
            const uint32_t base = ITEM_ADDR(IT_W1 + i);
            uint32_t b0, b1, b2, b3;
#pragma unroll
            for (int jp = 0; jp < 2; jp++) {
                ldsm_x4_t(base + lrow * W1_PITCH + (jp ? w1o1 : w1o0), b0, b1, b2, b3);
                mma16816(ch[jp * 2], xa[i * 3], 0u, xa[i * 3 + 1], 0u, b0, b1);
                mma16816(ch[jp * 2 + 1], xa[i * 3], 0u, xa[i * 3 + 1], 0u, b2, b3);
            }
            ldsm_x4_t(base + (16 + (lane & 7)) * W1_PITCH + w1o2, b0, b1, b2, b3);
            mma1688(ch[0], xa[i * 3 + 2], 0u, b0);
            mma1688(ch[1], xa[i * 3 + 2], 0u, b1);
            mma1688(ch[2], xa[i * 3 + 2], 0u, b2);
            mma1688(ch[3], xa[i * 3 + 2], 0u, b3);
            if (has5) {
                ldsm_x2_t(base + lrow * W1_PITCH + w1o3, b0, b1);
                mma16816(ch[4], xa[i * 3], 0u, xa[i * 3 + 1], 0u, b0, b1);
                ldsm_x1_t(base + (16 + (lane & 7)) * W1_PITCH + w1o3, b0);
                mma1688(ch[4], xa[i * 3 + 2], 0u, b0);
            }
            ITEM_DONE(IT_W1 + i);
        }
        if (g < 4) {
#pragma unroll
            for (int j = 0; j < 5; j++) {
                if (j < 4 || has5) {
                    const int col = (ht0 + j) * 8 + 2 * t;
                    const int dr = col / 36, c = col - dr * 36;
                    st_async_v2(mapa(sb + OFF_HBUF + ((r * 4 + g) * 36 + c) * 4, dr), ch[j][0], ch[j][1],
                                mapa(bar0 + BAR_H1 * 8, dr));
                }
            }
        }
    }
    {
        mbar_wait_cluster(bar0 + BAR_Q * 8, 0);
        const float* qb = reinterpret_cast<const float*>(sp + OFF_QBUF);
        float qs = 0.f;
#pragma unroll
        for (int s = 0; s < 8; s++) qs += qb[s * 256 + tid];
        *reinterpret_cast<bf16*>(sp + OFF_Q + (tid >> 7) * 272 + (tid & 127) * 2) = __float2bfloat16_rn(qs);
    }
    cbar();
    TL(4);

    float sc[4][4];
    {
        uint32_t qb0[8], qb1[8];
#pragma unroll
        for (int ks = 0; ks < 8; ks++) {
            qb0[ks] = (g < 2) ? lds32(sb + OFF_Q + g * 272 + (ks * 16 + 2 * t) * 2) : 0u;
            qb1[ks] = (g < 2) ? lds32(sb + OFF_Q + g * 272 + (ks * 16 + 8 + 2 * t) * 2) : 0u;
        }
        const int mt = warp & 3, par = warp >> 2;
        const int krow = mt * 16 + lrow;
#pragma unroll
        for (int s = 0; s < 8; s++) {
            if (s == 4 && warp >= 5) {
                const int i = tid - 160;
                if (i < 72) {
                    mbar_wait_cluster(bar0 + BAR_H1 * 8, 0);
                    const float2* hb = reinterpret_cast<const float2*>(sp + OFF_HBUF);
                    float a = 0.f, c = 0.f;
#pragma unroll
                    for (int k = 0; k < 8; k++) { float2 v = hb[k * 72 + i]; a += v.x; c += v.y; }
                    const int b = i / 18, pr = i - b * 18;
                    st_ll(g_h + (grp * 4 + b) * 144 + r * 18 + pr, pack_bf16(silu_f(bfr(a)), silu_f(bfr(c))), tag);
                }
                __syncwarp();
            }
            ITEM_WAIT(IT_K + s);
            if ((s & 1) == par) {
                float c0[4] = {0.f, 0.f, 0.f, 0.f}, c1[4] = {0.f, 0.f, 0.f, 0.f};
                const uint32_t base = ITEM_ADDR(IT_K + s) + krow * 128;
#pragma unroll
                for (int ks = 0; ks < 8; ks++) {
                    uint32_t a0, a1, a2, a3;
                    const int chunk = (ks & 3) * 2 + ltile;
                    ldsm_x4(base + (ks >> 2) * 8192 + ((chunk ^ (krow & 7)) << 4), a0, a1, a2, a3);
                    if (ks & 1) mma16816(c1, a0, a1, a2, a3, qb0[ks], qb1[ks]);
                    else mma16816(c0, a0, a1, a2, a3, qb0[ks], qb1[ks]);
                }
#pragma unroll
                for (int j = 0; j < 4; j++) sc[s >> 1][j] = bfr(bfr(c0[j] + c1[j]) * 0.08838834764831845f);
            }
            ITEM_DONE(IT_K + s);
        }
    }
    TL(5);
    float mh0, mh1;
    {
        float m0 = fmaxf(fmaxf(fmaxf(sc[0][0], sc[0][2]), fmaxf(sc[1][0], sc[1][2])),
                         fmaxf(fmaxf(sc[2][0], sc[2][2]), fmaxf(sc[3][0], sc[3][2])));
        float m1 = fmaxf(fmaxf(fmaxf(sc[0][1], sc[0][3]), fmaxf(sc[1][1], sc[1][3])),
                         fmaxf(fmaxf(sc[2][1], sc[2][3]), fmaxf(sc[3][1], sc[3][3])));
#pragma unroll
        for (int o = 16; o >= 4; o >>= 1) {
            m0 = fmaxf(m0, __shfl_xor_sync(0xffffffffu, m0, o));
            m1 = fmaxf(m1, __shfl_xor_sync(0xffffffffu, m1, o));
        }
        if (lane == 0) *reinterpret_cast<float2*>(sp + OFF_WMAX + warp * 8) = make_float2(m0, m1);
        cbar();
        const float4 w0 = lds128(sb + OFF_WMAX), w1v = lds128(sb + OFF_WMAX + 16), w2v = lds128(sb + OFF_WMAX + 32),
                     w3 = lds128(sb + OFF_WMAX + 48);
        m0 = fmaxf(fmaxf(fmaxf(w0.x, w0.z), fmaxf(w1v.x, w1v.z)), fmaxf(fmaxf(w2v.x, w2v.z), fmaxf(w3.x, w3.z)));
        m1 = fmaxf(fmaxf(fmaxf(w0.y, w0.w), fmaxf(w1v.y, w1v.w)), fmaxf(fmaxf(w2v.y, w2v.w), fmaxf(w3.y, w3.w)));
        mh0 = m0; mh1 = m1;
        float s0 = 0.f, s1 = 0.f;
        if (t == 0) {
            const int mt = warp & 3, par = warp >> 2;
            bf16* ps = reinterpret_cast<bf16*>(sp + OFF_P);
#pragma unroll
            for (int i = 0; i < 4; i++) {
                const int key = (par + 2 * i) * 64 + mt * 16 + g;
                bf16 p00 = __float2bfloat16_rn(__expf(sc[i][0] - m0));
                bf16 p01 = __float2bfloat16_rn(__expf(sc[i][1] - m1));
                bf16 p10 = __float2bfloat16_rn(__expf(sc[i][2] - m0));
                bf16 p11 = __float2bfloat16_rn(__expf(sc[i][3] - m1));
                ps[key] = p00; ps[520 + key] = p01; ps[key + 8] = p10; ps[520 + key + 8] = p11;
                s0 += __bfloat162float(p00) + __bfloat162float(p10);
                s1 += __bfloat162float(p01) + __bfloat162float(p11);
            }
        }
#pragma unroll
        for (int o = 16; o >= 4; o >>= 1) {
            s0 += __shfl_xor_sync(0xffffffffu, s0, o);
            s1 += __shfl_xor_sync(0xffffffffu, s1, o);
        }
        if (lane == 0) *reinterpret_cast<float2*>(sp + OFF_WSUM + warp * 8) = make_float2(s0, s1);
    }
    TL(6);
    cbar();
    TL(7);
    {
        float c0[4] = {0.f, 0.f, 0.f, 0.f}, c1[4] = {0.f, 0.f, 0.f, 0.f};
        const int vrow = (lane & 7) + (lane >> 4) * 8;
        const int chunk = (warp & 3) * 2 + ((lane >> 3) & 1);
        const uint32_t hoff = (warp >> 2) * 8192;
        const uint2* hsrc = g_h + (2 * r) * 576 + tid * 2;
        const bool has3 = tid < 64;
        uint4 hv0, hv1, hv2;
        hv2.y = tag; hv2.w = tag; hv2.x = 0; hv2.z = 0;
#pragma unroll
        for (int s = 0; s < 8; s++) {
            if (s == HG0) {
                hv0 = ld_ll2(hsrc);
                hv1 = ld_ll2(hsrc + 512);
                if (has3) hv2 = ld_ll2(hsrc + 1024);
            }
            if (s == HG1) {
                unsigned it = 0;
                while ((hv0.y != tag || hv0.w != tag || hv1.y != tag || hv1.w != tag || hv2.y != tag || hv2.w != tag) &&
                       ++it < SPIN_MAX) {
                    hv0 = ld_ll2(hsrc);
                    hv1 = ld_ll2(hsrc + 512);
                    if (has3) hv2 = ld_ll2(hsrc + 1024);
                }
#pragma unroll
                for (int k = 0; k < 3; k++) {
                    const int pi = tid + k * 256;
                    if (k < 2 || has3) {
                        const int gs = pi / 288, rem = pi - gs * 288, b = rem / 72, j = rem - b * 72;
                        const uint4 v = (k == 0) ? hv0 : ((k == 1) ? hv1 : hv2);
                        *reinterpret_cast<uint2*>(sp + OFF_HS + b * HS_PITCH + (gs * 288 + 4 * j) * 2) = make_uint2(v.x, v.z);
                    }
                }
            }
            ITEM_WAIT(IT_V + s);
            const uint32_t base = ITEM_ADDR(IT_V + s) + hoff;
#pragma unroll
            for (int ks = 0; ks < 4; ks++) {
                uint32_t a0, a1, a2, a3;
                const int row = ks * 16 + vrow;
                ldsm_x4_t(base + row * 128 + ((chunk ^ (row & 7)) << 4), a0, a1, a2, a3);
                uint32_t b0 = (g < 2) ? lds32(sb + OFF_P + g * 1040 + (s * 64 + ks * 16 + 2 * t) * 2) : 0u;
                uint32_t b1 = (g < 2) ? lds32(sb + OFF_P + g * 1040 + (s * 64 + ks * 16 + 8 + 2 * t) * 2) : 0u;
                if (ks & 1) mma16816(c1, a0, a1, a2, a3, b0, b1);
                else mma16816(c0, a0, a1, a2, a3, b0, b1);
            }
            ITEM_DONE(IT_V + s);
        }
        const float oa0 = c0[0] + c1[0], oa1 = c0[1] + c1[1], oa2 = c0[2] + c1[2], oa3 = c0[3] + c1[3];
        const float keep0 = split ? oa1 : oa0, keep1 = split ? oa3 : oa2;
        const float send0 = split ? oa0 : oa1, send1 = split ? oa2 : oa3;
        const int d = warp * 16 + g;
        const uint32_t rb = mapa(bar0 + BAR_O * 8, r ^ 1);
        if (t == 0) {
            const uint32_t ra = mapa(sb + OFF_OBUF + d * 4, r ^ 1);
            st_async_b32(ra, __float_as_uint(send0), rb);
            st_async_b32(ra + 32, __float_as_uint(send1), rb);
        }
        const float4 w0 = lds128(sb + OFF_WSUM), w1v = lds128(sb + OFF_WSUM + 16), w2v = lds128(sb + OFF_WSUM + 32),
                     w3 = lds128(sb + OFF_WSUM + 48);
        const float l0 = ((w0.x + w0.z) + (w1v.x + w1v.z)) + ((w2v.x + w2v.z) + (w3.x + w3.z));
        const float l1 = ((w0.y + w0.w) + (w1v.y + w1v.w)) + ((w2v.y + w2v.w) + (w3.y + w3.w));
        if (tid == 1) st_async_v2(mapa(sb + OFF_OBUF + 128 * 4, r ^ 1), split ? mh0 : mh1, split ? l0 : l1, rb);
        TL(8);
        const float mk = split ? mh1 : mh0, lk = split ? l1 : l0;
        mbar_wait_cluster(bar0 + BAR_O * 8, 0);
        const float* ob = reinterpret_cast<const float*>(sp + OFF_OBUF);
        const float mp = ob[128], lp = ob[129];
        const float p0 = ob[d], p1 = ob[d + 8];
        const float M = fmaxf(mk, mp);
        float ek = __expf(mk - M), ep = __expf(mp - M);
        const float inv = __fdividef(1.0f, lk * ek + lp * ep);
        ek *= inv; ep *= inv;
        const float f0 = keep0 * ek + p0 * ep, f1 = keep1 * ek + p1 * ep;
        const float n0 = __shfl_down_sync(0xffffffffu, f0, 4), n1 = __shfl_down_sync(0xffffffffu, f1, 4);
        if (t == 0 && (g & 1) == 0) {
            uint2* dst = g_o + (grp * 4 + bb) * 128 + split * 64 + (d >> 1);
            st_ll(dst, pack_bf16(f0, n0), tag);
            st_ll(dst + 4, pack_bf16(f1, n1), tag);
        }
    }
    TL(9);
    cbar();
    float co[5][4], cs[5][4];
#pragma unroll
    for (int j = 0; j < 5; j++)
#pragma unroll
        for (int i = 0; i < 4; i++) { co[j][i] = 0.f; cs[j][i] = 0.f; }
#pragma unroll
    for (int i = 0; i < 3; i++) {
        ITEM_WAIT(IT_W2 + i);
#pragma unroll
        for (int kk = 0; kk < 2; kk++) {
            const int kl = ((warp + 4 * i) & 7) + 8 * kk;
            if (kl < 12) {
                const int ks = i * 12 + kl;
                const uint32_t a0 = (g < 4) ? lds32(sb + OFF_HS + g * HS_PITCH + (ks * 16 + 2 * t) * 2) : 0u;
                const uint32_t a2 = (g < 4) ? lds32(sb + OFF_HS + g * HS_PITCH + (ks * 16 + 8 + 2 * t) * 2) : 0u;
                const uint32_t base = ITEM_ADDR(IT_W2 + i) + (kl * 16 + lrow) * WO_PITCH;
                uint32_t b0, b1, b2, b3;
                ldsm_x4_t(base + ltile * 16, b0, b1, b2, b3);
                mma16816(co[0], a0, 0u, a2, 0u, b0, b1);
                mma16816(co[1], a0, 0u, a2, 0u, b2, b3);
                ldsm_x4_t(base + (2 + ltile) * 16, b0, b1, b2, b3);
                mma16816(co[2], a0, 0u, a2, 0u, b0, b1);
                mma16816(co[3], a0, 0u, a2, 0u, b2, b3);
                ldsm_x2_t(base + 64, b0, b1);
                mma16816(co[4], a0, 0u, a2, 0u, b0, b1);
            }
        }
        ITEM_DONE(IT_W2 + i);
    }
    TL(10);
    {
        const uint2* src = g_o + (2 * r) * 512 + tid * 2;
        uint4 v0, v1;
        unsigned it = 0;
        do {
            v0 = ld_ll2(src);
            v1 = ld_ll2(src + 512);
        } while ((v0.y != tag || v0.w != tag || v1.y != tag || v1.w != tag) && ++it < SPIN_MAX);
        const int b = tid >> 6, j = tid & 63;
        *reinterpret_cast<uint2*>(sp + OFF_OS + b * OS_PITCH + (4 * j) * 2) = make_uint2(v0.x, v0.z);
        *reinterpret_cast<uint2*>(sp + OFF_OS + b * OS_PITCH + (256 + 4 * j) * 2) = make_uint2(v1.x, v1.z);
    }
    cbar();
    TL(11);
#pragma unroll
    for (int i = 0; i < 3; i++) {
        mbar_wait_cluster(bar0 + (BAR_FULL + (IT_WO + i) % NSLOT) * 8, ((IT_WO + i) / NSLOT) & 1);
#pragma unroll
        for (int kk = 0; kk < 2; kk++) {
            const int kl = ((warp + 4 * i) & 7) + 8 * kk;
            if (kl < ((i < 2) ? 12 : 8)) {
                const int ks = i * 12 + kl;
                const uint32_t a0 = (g < 4) ? lds32(sb + OFF_OS + g * OS_PITCH + (ks * 16 + 2 * t) * 2) : 0u;
                const uint32_t a2 = (g < 4) ? lds32(sb + OFF_OS + g * OS_PITCH + (ks * 16 + 8 + 2 * t) * 2) : 0u;
                const uint32_t base = ITEM_ADDR(IT_WO + i) + (kl * 16 + lrow) * WO_PITCH;
                uint32_t b0, b1, b2, b3;
                ldsm_x4_t(base + ltile * 16, b0, b1, b2, b3);
                mma16816(cs[0], a0, 0u, a2, 0u, b0, b1);
                mma16816(cs[1], a0, 0u, a2, 0u, b2, b3);
                ldsm_x4_t(base + (2 + ltile) * 16, b0, b1, b2, b3);
                mma16816(cs[2], a0, 0u, a2, 0u, b0, b1);
                mma16816(cs[3], a0, 0u, a2, 0u, b2, b3);
                ldsm_x2_t(base + 64, b0, b1);
                mma16816(cs[4], a0, 0u, a2, 0u, b0, b1);
            }
        }
    }
    {
        float* red = reinterpret_cast<float*>(sp + OFF_RED);
        if (g < 4) {
#pragma unroll
            for (int j = 0; j < 5; j++) {
                *reinterpret_cast<float2*>(red + warp * 320 + g * 40 + j * 8 + 2 * t) = make_float2(cs[j][0], cs[j][1]);
                *reinterpret_cast<float2*>(red + warp * 320 + 160 + g * 40 + j * 8 + 2 * t) = make_float2(co[j][0], co[j][1]);
            }
        }
        cbar();
        TL(12);
        const int coff = 4 * (grp & 1);
#pragma unroll
        for (int k = 0; k < 2; k++) {
            const int vi = tid + k * 256;
            if (vi < 288) {
                const int which = vi / 144, el = vi - which * 144;
                const int b = el / 36, c = el - b * 36;
                const int ri = which * 160 + b * 40 + coff + c;
                float v[8];
#pragma unroll
                for (int w = 0; w < 8; w++) v[w] = red[w * 320 + ri];
                const float a = ((v[0] + v[1]) + (v[2] + v[3])) + ((v[4] + v[5]) + (v[6] + v[7]));
                const int dr = el / 18, e = el - dr * 18;
                st_async_b32(mapa(sb + OFF_FBUF + ((r * 2 + which) * 18 + e) * 4, dr), __float_as_uint(a),
                             mapa(bar0 + BAR_F * 8, dr));
            }
        }
        if (warp == 0) {
            mbar_wait_cluster(bar0 + BAR_F * 8, 0);
            if (lane < 18) {
                const float* f = reinterpret_cast<const float*>(sp + OFF_FBUF) + lane;
                const float sv = ((f[0] + f[36]) + (f[72] + f[108])) + ((f[144] + f[180]) + (f[216] + f[252]));
                const float ov = ((f[18] + f[54]) + (f[90] + f[126])) + ((f[162] + f[198]) + (f[234] + f[270]));
                const float gv = bfr(silu_f(bfr(ov)));
                out[xoi] = __float2bfloat16_rn(xres + bfr(bfr(sv) * gv));
            }
        }
    }
    TL(13);
    if (tid == 0) g_epoch[cta] = tag;
}

#define L2PROMO CU_TENSOR_MAP_L2_PROMOTION_L2_64B
#define L2PROMO3 CU_TENSOR_MAP_L2_PROMOTION_L2_128B
typedef CUresult (*PFN_encodeTiled)(CUtensorMap*, CUtensorMapDataType, cuuint32_t, void*, const cuuint64_t*,
                                    const cuuint64_t*, const cuuint32_t*, const cuuint32_t*, CUtensorMapInterleave,
                                    CUtensorMapSwizzle, CUtensorMapL2promotion, CUtensorMapFloatOOBfill);

void make_map(PFN_encodeTiled fn, CUtensorMap* m, const void* ptr, uint64_t cols, uint64_t rows, uint32_t bc, uint32_t br,
              CUtensorMapSwizzle sw) {
    cuuint64_t dims[2] = {cols, rows};
    cuuint64_t strides[1] = {cols * 2};
    cuuint32_t box[2] = {bc, br};
    cuuint32_t es[2] = {1, 1};
    fn(m, CU_TENSOR_MAP_DATA_TYPE_BFLOAT16, 2, const_cast<void*>(ptr), dims, strides, box, es,
       CU_TENSOR_MAP_INTERLEAVE_NONE, sw, L2PROMO, CU_TENSOR_MAP_FLOAT_OOB_FILL_NONE);
}

void make_map3(PFN_encodeTiled fn, CUtensorMap* m, const void* ptr, uint64_t cols, uint64_t rows, uint32_t bc, uint32_t br,
               uint32_t nb, CUtensorMapSwizzle sw) {
    cuuint64_t dims[3] = {bc, rows, cols / bc};
    cuuint64_t strides[2] = {cols * 2, (cuuint64_t)bc * 2};
    cuuint32_t box[3] = {bc, br, nb};
    cuuint32_t es[3] = {1, 1, 1};
    fn(m, CU_TENSOR_MAP_DATA_TYPE_BFLOAT16, 3, const_cast<void*>(ptr), dims, strides, box, es,
       CU_TENSOR_MAP_INTERLEAVE_NONE, sw, L2PROMO3, CU_TENSOR_MAP_FLOAT_OOB_FILL_NONE);
}

}

extern "C" void kernel_launch(void* const* d_in, const int* in_sizes, int n_in, void* d_out, int out_size) {
    const bf16* x = (const bf16*)d_in[0];
    const bf16* kc = (const bf16*)d_in[1];
    const bf16* vc = (const bf16*)d_in[2];
    const bf16* wq = (const bf16*)d_in[3];
    const bf16* wo = (const bf16*)d_in[4];
    const bf16* w1 = (const bf16*)d_in[6];
    const bf16* w2 = (const bf16*)d_in[7];

    static PFN_encodeTiled fn = nullptr;
    if (!fn) {
        void* p = nullptr;
        cudaDriverEntryPointQueryResult qr;
        cudaGetDriverEntryPoint("cuTensorMapEncodeTiled", &p, cudaEnableDefault, &qr);
        fn = (PFN_encodeTiled)p;
        cudaFuncSetAttribute(fused_decode_kernel, cudaFuncAttributeMaxDynamicSharedMemorySize, SMEM_BYTES);
    }
    CUtensorMap tmWq, tmK, tmW1, tmV, tmWo, tmW2;
    make_map3(fn, &tmWq, wq, 4096, DM, 64, 24, 4, CU_TENSOR_MAP_SWIZZLE_128B);
    make_map3(fn, &tmW1, w1, FF, DM, 72, 24, 4, CU_TENSOR_MAP_SWIZZLE_NONE);
    make_map3(fn, &tmK, kc, DH, (uint64_t)4 * HKV * SK, 64, 64, 2, CU_TENSOR_MAP_SWIZZLE_128B);
    make_map3(fn, &tmV, vc, DH, (uint64_t)4 * HKV * SK, 64, 64, 2, CU_TENSOR_MAP_SWIZZLE_128B);
    make_map(fn, &tmWo, wo, DM, 4096, 40, 64, CU_TENSOR_MAP_SWIZZLE_NONE);
    make_map(fn, &tmW2, w2, DM, FF, 40, 64, CU_TENSOR_MAP_SWIZZLE_NONE);

    cudaLaunchConfig_t cfg = {};
    cfg.gridDim = dim3(NCTA);
    cfg.blockDim = dim3(NTHREADS);
    cfg.dynamicSmemBytes = SMEM_BYTES;
    cfg.stream = cudaStreamPerThread;
    cudaLaunchAttribute at[1];
    at[0].id = cudaLaunchAttributeClusterDimension;
    at[0].val.clusterDim.x = 8;
    at[0].val.clusterDim.y = 1;
    at[0].val.clusterDim.z = 1;
    cfg.attrs = at;
    cfg.numAttrs = 1;
    cudaLaunchKernelEx(&cfg, fused_decode_kernel, tmWq, tmK, tmW1, tmV, tmWo, tmW2, x, (bf16*)d_out);
}
```
